```python
import torch

def _softmax(x, axis=-1):
    return torch.softmax(x, dim=axis)
def _gelu(x):
    return torch.nn.functional.gelu(x, approximate="tanh")
def _silu(x):
    return torch.nn.functional.silu(x)
def _sigmoid(x):
    return torch.sigmoid(x)
def _layernorm(x, axis=-1, eps=1e-5):
    m = x.mean(dim=axis, keepdim=True)
    v = x.var(dim=axis, keepdim=True, unbiased=False)
    return (x - m) / torch.sqrt(v + eps)
def _scatter_add(tgt, idx, src, axis=0):
    return tgt.clone().index_add_(axis, idx, src)
def _segment_sum(src, seg, n):
    out = torch.zeros((n,) + src.shape[1:], dtype=src.dtype)
    return out.index_add_(0, seg, src)
def _pad(x, pw):
    flat = tuple(v for pair in reversed(pw) for v in pair)
    return torch.nn.functional.pad(x, flat)

kernel_name = 'standalone__sliding_block_cached__decode'

def setup_inputs():

    _w = (lambda a: (lambda t: t.to(torch.bfloat16) if t.is_floating_point() else t)(torch.as_tensor(a)))
    B, Sq, D = 4, 1, 448
    Hq, Hkv, Sk, Dh = 16, 8, 4096, 256
    assert Hq % Hkv == 0, (Hq, Hkv)
    return {
        "x": _w((lambda *s: torch.randn(*s, dtype=torch.bfloat16) * 0.8)(B, Sq, D)),
        "k_cache": _w((lambda *s: torch.randn(*s, dtype=torch.bfloat16) * 0.8)(B, Hkv, Sk, Dh)),
        "v_cache": _w((lambda *s: torch.randn(*s, dtype=torch.bfloat16) * 0.05)(B, Hkv, Sk, Dh)),
        "wq": _w((lambda *s: torch.randn(*s, dtype=torch.bfloat16) * 0.8)(D, Hq * Dh) * (D ** -0.5)),
        "wo": _w((lambda *s: torch.randn(*s, dtype=torch.bfloat16) * 0.05)(Hq * Dh, D) * ((Hq * Dh) ** -0.5)),
    }

def reference(x, k_cache, v_cache, wq, wo):
    B, Sq, D = x.shape
    Hq, Dh = 16, 256
    Hkv, Sk = k_cache.shape[1], k_cache.shape[2]
    W = min(4096, max(256, Sk // 4))
    rep = Hq // Hkv
    q = (lambda x, *d: x.permute(*d))((x @ wq).reshape(B, Sq, Hq, Dh), 0, 2, 1, 3)
    k = (lambda x, n, axis: torch.repeat_interleave(x, n, dim=axis))(k_cache[:, :, Sk - W:, :], rep, axis=1)
    v = (lambda x, n, axis: torch.repeat_interleave(x, n, dim=axis))(v_cache[:, :, Sk - W:, :], rep, axis=1)
    scores = torch.einsum("bhqd,bhkd->bhqk", q, k) * (Dh ** -0.5)
    p = _softmax(scores, axis=-1)
    o = torch.einsum("bhqk,bhkd->bhqd", p, v)
    return (lambda x, *d: x.permute(*d))(o, 0, 2, 1, 3).reshape(B, Sq, Hq * Dh) @ wo
```

```cpp
#include <cuda_runtime.h>
#include <cuda_bf16.h>
#include <cuda.h>
#include <stdint.h>

namespace {

constexpr int NCTA = 128;
constexpr int NTHREADS = 14 * 32;

constexpr int SLOT = 32768;
constexpr int OFF_WQ = 6 * SLOT;
constexpr int OFF_X = OFF_WQ + 28672;
constexpr int OFF_MISC = OFF_X + 3584;
constexpr int OFF_RED = OFF_MISC;
constexpr int OFF_Q = OFF_RED + 2048;
constexpr int OFF_STAT = OFF_Q + 1056;
constexpr int OFF_BAR = OFF_STAT + 128;
constexpr int SMEM_BYTES = OFF_BAR + 160;
constexpr int OFF_P = 3 * SLOT;
constexpr int OFF_O = OFF_P + 2048;
constexpr int OFF_WO = OFF_WQ;
constexpr int WO_ROWB = 240;
static_assert(SMEM_BYTES <= 232448, "smem");

enum { B_WQ = 0, B_K0 = 1, B_V0 = 5, B_WO = 13, NOPS = 17, B_FREE0 = 17, B_FREE1 = 18, B_FREE2 = 19, NBARS = 20 };

#define FENCE0 0
#define PFMAP 1
#define PFTLB 0
#define ACC_STRIDE 512
struct alignas(1024) Scratch {
    uint32_t q[4 * 4096];
    uint32_t o[NCTA * 512];
    float acc[112 * ACC_STRIDE];
    uint32_t lse[NCTA * 8];
    uint32_t cnt_o[8 * 32];
    uint32_t cnt_z[32];
};
__device__ Scratch g_s;

#define TS(i)
#define TS_DECL
#define TS_FLUSH(i)

__device__ __forceinline__ uint32_t gtime_lo() { uint32_t t; asm volatile("mov.u32 %0, %globaltimer_lo;" : "=r"(t)); return t; }
constexpr int SPIN_LIMIT = 1 << 22;

__device__ __forceinline__ void mbar_init(uint32_t bar, uint32_t cnt) {
    asm volatile("mbarrier.init.shared::cta.b64 [%0], %1;" ::"r"(bar), "r"(cnt) : "memory");
}
__device__ __forceinline__ void mbar_expect_tx(uint32_t bar, uint32_t bytes) {
    asm volatile("mbarrier.arrive.expect_tx.shared::cta.b64 _, [%0], %1;" ::"r"(bar), "r"(bytes) : "memory");
}
__device__ __forceinline__ void mbar_arrive(uint32_t bar) {
    asm volatile("mbarrier.arrive.shared::cta.b64 _, [%0];" ::"r"(bar) : "memory");
}
__device__ __forceinline__ void mbar_wait(uint32_t bar) {
    uint32_t ok;
    int it = 0;
    do {
        asm volatile("{.reg .pred p; mbarrier.try_wait.parity.shared::cta.b64 p, [%1], 0; selp.u32 %0,1,0,p;}"
                     : "=r"(ok) : "r"(bar) : "memory");
        if (++it > SPIN_LIMIT) __trap();
    } while (!ok);
}
__device__ __forceinline__ uint32_t mbar_test(uint32_t bar, uint32_t parity) {
    uint32_t ok;
    asm volatile("{.reg .pred p; mbarrier.test_wait.parity.shared::cta.b64 p, [%1], %2; selp.u32 %0,1,0,p;}"
                 : "=r"(ok) : "r"(bar), "r"(parity) : "memory");
    return ok;
}
__device__ __forceinline__ void tma3d(uint32_t dst, const CUtensorMap* tm, int c0, int c1, int c2, uint32_t bar) {
    asm volatile("cp.async.bulk.tensor.3d.shared::cluster.global.mbarrier::complete_tx::bytes [%0], [%1, {%3,%4,%5}], [%2];"
                 ::"r"(dst), "l"(tm), "r"(bar), "r"(c0), "r"(c1), "r"(c2) : "memory");
}
__device__ __forceinline__ void tma2d(uint32_t dst, const CUtensorMap* tm, int c0, int c1, uint32_t bar) {
    asm volatile("cp.async.bulk.tensor.2d.shared::cluster.global.mbarrier::complete_tx::bytes [%0], [%1, {%3,%4}], [%2];"
                 ::"r"(dst), "l"(tm), "r"(bar), "r"(c0), "r"(c1) : "memory");
}
__device__ __forceinline__ void bulk_g2s(uint32_t dst, const void* src, uint32_t bytes, uint32_t bar) {
    asm volatile("cp.async.bulk.shared::cluster.global.mbarrier::complete_tx::bytes [%0], [%1], %2, [%3];"
                 ::"r"(dst), "l"(src), "r"(bytes), "r"(bar) : "memory");
}
__device__ __forceinline__ void ldsm4(uint32_t addr, uint32_t& r0, uint32_t& r1, uint32_t& r2, uint32_t& r3) {
    asm volatile("ldmatrix.sync.aligned.m8n8.x4.shared.b16 {%0,%1,%2,%3}, [%4];"
                 : "=r"(r0), "=r"(r1), "=r"(r2), "=r"(r3) : "r"(addr) : "memory");
}
__device__ __forceinline__ void ldsm2(uint32_t addr, uint32_t& r0, uint32_t& r1) {
    asm volatile("ldmatrix.sync.aligned.m8n8.x2.shared.b16 {%0,%1}, [%2];"
                 : "=r"(r0), "=r"(r1) : "r"(addr) : "memory");
}
__device__ __forceinline__ void ldsm4t(uint32_t addr, uint32_t& r0, uint32_t& r1, uint32_t& r2, uint32_t& r3) {
    asm volatile("ldmatrix.sync.aligned.m8n8.x4.trans.shared.b16 {%0,%1,%2,%3}, [%4];"
                 : "=r"(r0), "=r"(r1), "=r"(r2), "=r"(r3) : "r"(addr) : "memory");
}
__device__ __forceinline__ void mma16816(float (&c)[4], uint32_t a0, uint32_t a1, uint32_t a2, uint32_t a3,
                                         uint32_t b0, uint32_t b1) {
    asm volatile("mma.sync.aligned.m16n8k16.row.col.f32.bf16.bf16.f32 {%0,%1,%2,%3}, {%4,%5,%6,%7}, {%8,%9}, {%0,%1,%2,%3};"
                 : "+f"(c[0]), "+f"(c[1]), "+f"(c[2]), "+f"(c[3])
                 : "r"(a0), "r"(a1), "r"(a2), "r"(a3), "r"(b0), "r"(b1));
}
__device__ __forceinline__ void bar_sync(int id, int n) { asm volatile("bar.sync %0, %1;" ::"r"(id), "r"(n) : "memory"); }
__device__ __forceinline__ void bar_arrive(int id, int n) { asm volatile("bar.arrive %0, %1;" ::"r"(id), "r"(n) : "memory"); }
__device__ __forceinline__ uint4 ld_poll4(const uint32_t* p) {
    uint4 v;
    asm volatile("ld.relaxed.gpu.global.v4.u32 {%0,%1,%2,%3}, [%4];"
                 : "=r"(v.x), "=r"(v.y), "=r"(v.z), "=r"(v.w) : "l"(p) : "memory");
    return v;
}
__device__ __forceinline__ void red_inc(uint32_t* p) {
    asm volatile("red.relaxed.gpu.global.add.u32 [%0], 1;" ::"l"(p) : "memory");
}
__device__ __forceinline__ void wait_count(const uint32_t* p, uint32_t target) {
    uint32_t v;
    int it = 0;
    do {
        asm volatile("ld.relaxed.gpu.global.u32 %0, [%1];" : "=r"(v) : "l"(p) : "memory");
        if (++it > SPIN_LIMIT) __trap();
    } while (v != target);
}
__device__ __forceinline__ void st_pub(uint32_t* p, uint32_t v) {
    asm volatile("st.relaxed.gpu.global.u32 [%0], %1;" ::"l"(p), "r"(v) : "memory");
}
__device__ __forceinline__ void st_pub2(uint32_t* p, uint32_t a, uint32_t b) {
    asm volatile("st.relaxed.gpu.global.v2.u32 [%0], {%1,%2};" ::"l"(p), "r"(a), "r"(b) : "memory");
}
__device__ __forceinline__ void st_pub4(uint32_t* p, uint32_t a, uint32_t b, uint32_t c, uint32_t d) {
    asm volatile("st.relaxed.gpu.global.v4.u32 [%0], {%1,%2,%3,%4};" ::"l"(p), "r"(a), "r"(b), "r"(c), "r"(d) : "memory");
}
__device__ __forceinline__ void sts16(uint32_t addr, uint16_t v) { asm volatile("st.shared.u16 [%0], %1;" ::"r"(addr), "h"(v) : "memory"); }
__device__ __forceinline__ void sts32f(uint32_t addr, float v) { asm volatile("st.shared.f32 [%0], %1;" ::"r"(addr), "f"(v) : "memory"); }
__device__ __forceinline__ void sts64(uint32_t addr, uint32_t a, uint32_t b) {
    asm volatile("st.shared.v2.u32 [%0], {%1,%2};" ::"r"(addr), "r"(a), "r"(b) : "memory");
}
__device__ __forceinline__ float lds32f(uint32_t addr) {
    float v;
    asm volatile("ld.shared.f32 %0, [%1];" : "=f"(v) : "r"(addr) : "memory");
    return v;
}
__device__ __forceinline__ uint16_t bf16bits(float v) { return __bfloat16_as_ushort(__float2bfloat16_rn(v)); }
__device__ __forceinline__ uint32_t tagf(float v, uint32_t tag) { return (__float_as_uint(v) & ~3u) | tag; }
__device__ __forceinline__ bool tag_ok4(const uint4& v, uint32_t tag) {
    return ((((v.x ^ tag) | (v.y ^ tag)) | ((v.z ^ tag) | (v.w ^ tag))) & 3u) == 0u;
}

template <int STRIDE>
__device__ __forceinline__ void gather4(uint4 (&v)[4], const uint32_t* src, uint32_t tag) {
    int it = 0;
    uint32_t bad;
    do {
#pragma unroll
        for (int s = 0; s < 4; s++) v[s] = ld_poll4(src + s * STRIDE);
        bad = 0;
#pragma unroll
        for (int s = 0; s < 4; s++) bad |= ((v[s].x ^ tag) | (v[s].y ^ tag)) | ((v[s].z ^ tag) | (v[s].w ^ tag));
        if (++it > SPIN_LIMIT) __trap();
    } while (bad & 3u);
}
__device__ __forceinline__ uint32_t ld_poll(const uint32_t* p) {
    uint32_t v;
    asm volatile("ld.relaxed.gpu.global.u32 %0, [%1];" : "=r"(v) : "l"(p) : "memory");
    return v;
}

template <typename T> __device__ __forceinline__ void pin(T*& p) { asm volatile("" : "+l"(p)); }
__device__ __forceinline__ void pin(uint32_t& v) { asm volatile("" : "+r"(v)); }

struct Params {
    CUtensorMap m[4];
    uint16_t due[20];
    int8_t dep[20];
    int8_t order[20];
    int qgate, lgate, stagger;
    const char* vptr;
    const char* woptr;
};

__global__ void __launch_bounds__(NTHREADS, 1)
fused_decode_kernel(const __grid_constant__ Params prm, const __nv_bfloat16* __restrict__ x, __nv_bfloat16* __restrict__ out) {
    extern __shared__ __align__(1024) uint8_t smem_raw[];
    const uint32_t sb = (uint32_t)__cvta_generic_to_shared(smem_raw);
    const int c = blockIdx.x;
    const int hkv = c >> 4, j = c & 15;
    const int warp = threadIdx.x >> 5, lane = threadIdx.x & 31;
    const uint32_t bars = sb + OFF_BAR;
    TS_DECL;

    const int row0 = ((j >> 2) * 8 + hkv) * 4096 + 3072 + (j & 3) * 256;
    const uint32_t t_start = gtime_lo();
    if (threadIdx.x == 12 * 32) {
        TS(0);
        mbar_init(bars + 8 * B_WQ, 1);
        mbar_init(bars + 8 * B_K0, 1);
        mbar_expect_tx(bars + 8 * B_WQ, 28672 + 3584);
        tma3d(sb + OFF_WQ, &prm.m[0], c * 32, 0, 0, bars + 8 * B_WQ);
        bulk_g2s(sb + OFF_X, x, 3584, bars + 8 * B_WQ);
        mbar_expect_tx(bars + 8 * B_K0, SLOT);
        tma3d(sb, &prm.m[1], 0, row0, 0, bars + 8 * B_K0);
#pragma unroll
        for (int i = 2; i < NOPS; i++) mbar_init(bars + 8 * i, 1);
        mbar_init(bars + 8 * B_FREE0, 4);
        mbar_init(bars + 8 * B_FREE1, 4);
        mbar_init(bars + 8 * B_FREE2, 8);
        asm volatile("fence.proxy.async.shared::cta;" ::: "memory");
        asm volatile("prefetch.tensormap [%0];" ::"l"(&prm.m[2]) : "memory");
        asm volatile("prefetch.tensormap [%0];" ::"l"(&prm.m[3]) : "memory");
    }
    const uint32_t* cnt_src = &g_s.cnt_o[hkv * 32];
    const uint32_t epoch = (ld_poll(cnt_src) >> 4) + 1u;
    const uint32_t tag = epoch & 3u;
    const int g = lane >> 2, t = lane & 3;
    __syncthreads();

    if (warp == 12) {
        const int i = min(lane, NOPS - 1);
        const bool isk = i < B_V0, iso = i >= B_WO;
        const CUtensorMap* tm = &prm.m[isk ? 1 : (iso ? 3 : 2)];
        uint32_t dst = sb + (isk ? (i - B_K0) * SLOT : (iso ? OFF_WO + (i - B_WO) * 32 * WO_ROWB : (((i - B_V0 + 8) % 12) * (SLOT / 2))));
        uint32_t c0 = iso ? (j & 3) * 112 : 0;
        uint32_t c1 = isk ? row0 + (i - B_K0) * 64 : (iso ? (c >> 2) * 128 + (i - B_WO) * 32 : row0 + (i - B_V0) * 32);
        uint32_t due = prm.due[i] + (iso ? (c >> 2 & 3) * prm.stagger : 0);
        const int dep = prm.dep[i];
        uint32_t mybar = bars + 8 * i;
        uint32_t depbar = dep >= 0 ? bars + 8 * dep : mybar, deppar = dep >= 0 ? 0 : 1;
        uint32_t frebar = i >= B_V0 + 4 ? bars + 8 * (B_FREE0 + min((i - B_V0 - 4) >> 1, 2)) : mybar, frepar = i >= B_V0 + 4 ? 0 : 1;
        pin(tm); pin(dst); pin(c0); pin(c1); pin(due); pin(mybar); pin(depbar); pin(deppar); pin(frebar); pin(frepar);
        bool pending = lane >= 2 && lane < NOPS;
        if (pending) mbar_expect_tx(mybar, isk ? SLOT : (iso ? 32 * WO_ROWB : SLOT / 2));
        int it = 0;
        do {
            const uint32_t now = gtime_lo() - t_start;
            if (pending && now >= due) {
                if (mbar_test(depbar, deppar) & mbar_test(frebar, frepar)) {
                    tma3d(dst, tm, c0, c1, 0, mybar);
                    pending = false;
                }
            }
            if (++it > SPIN_LIMIT) __trap();
        } while (__any_sync(0xffffffffu, pending));
        if (lane != 0) return;
        TS(1); TS_FLUSH(0); TS_FLUSH(1);
        return;
    }

    if (warp < 8) {
        uint32_t bf[32];
        {
            float acc[4] = {0.f, 0.f, 0.f, 0.f};
            const int d0 = (warp >> 1) * 112;
            const int ar = d0 + (lane & 7) + ((lane >> 4) << 3);
            const int ach = (warp & 1) * 2 + ((lane >> 3) & 1);
            const uint32_t aaddr = sb + OFF_WQ + ar * 64 + ((ach ^ ((ar >> 1) & 3)) << 4);
            const uint32_t baddr = sb + OFF_X + ((lane & 7) >> 1) * 896 + d0 * 2 + ((lane >> 3) & 1) * 16;
            mbar_wait(bars + 8 * B_WQ);
#pragma unroll
            for (int ks = 0; ks < 7; ks++) {
                uint32_t a0, a1, a2, a3, b0, b1;
                ldsm4t(aaddr + ks * 1024, a0, a1, a2, a3);
                ldsm2(baddr + ks * 32, b0, b1);
                mma16816(acc, a0, a1, a2, a3, b0, b1);
            }
            const uint32_t raddr = sb + OFF_RED + (((warp >> 1) * 4 + t) * 32 + (warp & 1) * 16 + g) * 4;
            sts32f(raddr, acc[0]);
            sts32f(raddr + 32, acc[2]);
            bar_arrive(1, 384);
            if (lane == 0) mbar_arrive(bars + 8 * B_FREE2);
        }
        bar_sync(2, 384);
        {
            const uint32_t qaddr = sb + OFF_Q + ((lane >> 1) & 1) * 528 + (lane >> 3) * 16;
#pragma unroll
            for (int i = 0; i < 8; i++) ldsm4(qaddr + i * 64, bf[4 * i], bf[4 * i + 1], bf[4 * i + 2], bf[4 * i + 3]);
        }
        float sc[4] = {0.f, 0.f, 0.f, 0.f};
        {
            const int kr = (warp & 3) * 16 + (lane & 7) + ((lane >> 3) & 1) * 8;
            const int chi = lane >> 4, sw = lane & 7;
#pragma unroll 1
            for (int r = 0; r < 2; r++) {
                const int chunk = (warp >> 2) + 2 * r;
                const uint32_t kbase = sb + chunk * SLOT + kr * 128;
                mbar_wait(bars + 8 * (B_K0 + chunk));
                float a[4] = {0.f, 0.f, 0.f, 0.f}, b[4] = {0.f, 0.f, 0.f, 0.f};
#pragma unroll
                for (int ks = 0; ks < 16; ks += 2) {
                    uint32_t a0, a1, a2, a3, e0, e1, e2, e3;
                    ldsm4(kbase + (ks >> 2) * 8192 + ((((ks & 3) * 2 + chi) ^ sw) << 4), a0, a1, a2, a3);
                    ldsm4(kbase + (ks >> 2) * 8192 + ((((ks & 3) * 2 + 2 + chi) ^ sw) << 4), e0, e1, e2, e3);
                    mma16816(a, a0, a1, a2, a3, bf[2 * ks], bf[2 * ks + 1]);
                    mma16816(b, e0, e1, e2, e3, bf[2 * ks + 2], bf[2 * ks + 3]);
                }
                sc[0] = sc[2];
                sc[1] = sc[3];
                sc[2] = a[0] + b[0];
                sc[3] = a[2] + b[2];
                __syncwarp();
                if (lane == 0 && r == 0) mbar_arrive(bars + 8 * (B_FREE0 + chunk));
            }
        }
        float inv_l;
        {
            const float cs = 0.0625f * 1.4426950408889634f;
            float m = fmaxf(fmaxf(sc[0], sc[1]), fmaxf(sc[2], sc[3]));
            m = fmaxf(m, __shfl_xor_sync(0xffffffffu, m, 4));
            m = fmaxf(m, __shfl_xor_sync(0xffffffffu, m, 8));
            m = fmaxf(m, __shfl_xor_sync(0xffffffffu, m, 16));
            if (lane < 2) sts32f(sb + OFF_STAT + (warp * 2 + lane) * 4, m);
            bar_sync(3, 256);
#pragma unroll
            for (int w = 0; w < 8; w++) m = fmaxf(m, lds32f(sb + OFF_STAT + (w * 2 + (t & 1)) * 4));
            const float mc = m * cs;
            float l = 0.f;
            const uint32_t paddr = sb + OFF_P + (t & 1) * 528 + ((warp >> 2) * 64 + (warp & 3) * 16 + g) * 2;
#pragma unroll
            for (int i = 0; i < 4; i++) {
                const float p = exp2f(fmaf(sc[i], cs, -mc));
                l += p;
                if (t < 2) sts16(paddr + (i >> 1) * 256 + (i & 1) * 16, bf16bits(p));
            }
            l += __shfl_xor_sync(0xffffffffu, l, 4);
            l += __shfl_xor_sync(0xffffffffu, l, 8);
            l += __shfl_xor_sync(0xffffffffu, l, 16);
            if (lane < 2) sts32f(sb + OFF_STAT + 64 + (warp * 2 + lane) * 4, l);
            bar_sync(3, 256);
            l = 0.f;
#pragma unroll
            for (int w = 0; w < 8; w++) l += lds32f(sb + OFF_STAT + 64 + (w * 2 + (t & 1)) * 4);
            inv_l = __frcp_rn(l);
            if (threadIdx.x < 8) st_pub(&g_s.lse[c * 8 + lane], tagf(mc + log2f(l), tag));
            if (threadIdx.x == 0) TS(4);
        }
        uint32_t v0, v1, pa, wa, oa;
        {
            const int vr = (lane & 7) + ((lane >> 4) << 3);
            const int ch = (warp & 1) * 4 + ((lane >> 3) & 1);
            v0 = sb + (warp >> 1) * 4096 + vr * 128 + ((ch ^ (lane & 7)) << 4);
            v1 = sb + (warp >> 1) * 4096 + vr * 128 + (((ch + 2) ^ (lane & 7)) << 4);
            pa = sb + OFF_P + ((lane >> 1) & 1) * 528 + (lane >> 3) * 16;
            wa = sb + OFF_WO + vr * WO_ROWB + (warp * 2 + ((lane >> 3) & 1)) * 16;
            oa = sb + OFF_O + ((lane & 7) >> 1) * 272 + (lane >> 3) * 16;
        }
        uint32_t* o_dst = &g_s.o[c * 512 + (t & 1) * 256 + warp * 32 + g * 4];
        float* acc_dst = &g_s.acc[(t * 28 + (j & 3) * 7 + warp) * ACC_STRIDE + g * 4];
        __nv_bfloat16* out_dst = out + (t * 28 + (j & 3) * 7 + warp) * 16 + g;
        uint32_t* cnt_o = &g_s.cnt_o[hkv * 32];
        pin(v0); pin(v1); pin(pa); pin(wa); pin(oa); pin(o_dst); pin(acc_dst); pin(out_dst); pin(cnt_o);
        float o0[4] = {0.f, 0.f, 0.f, 0.f}, o1[4] = {0.f, 0.f, 0.f, 0.f};
        float o2[4] = {0.f, 0.f, 0.f, 0.f}, o3[4] = {0.f, 0.f, 0.f, 0.f};
#pragma unroll 1
        for (int cq = 0; cq < 8; cq++) {
            const uint32_t so = ((cq < 4) ? 8 + cq : cq - 4) * (SLOT / 2);
            ldsm4(pa + cq * 64, bf[0], bf[1], bf[2], bf[3]);
            uint32_t va = v0 + so, vb = v1 + so;
            pin(va); pin(vb);
            mbar_wait(bars + 8 * (B_V0 + cq));
            if (cq == 7 && threadIdx.x == 224) red_inc(cnt_o);
            uint32_t a[16];
            ldsm4t(va, a[0], a[1], a[2], a[3]);
            ldsm4t(vb, a[4], a[5], a[6], a[7]);
            ldsm4t(va + 2048, a[8], a[9], a[10], a[11]);
            ldsm4t(vb + 2048, a[12], a[13], a[14], a[15]);
            mma16816(o0, a[0], a[1], a[2], a[3], bf[0], bf[1]);
            mma16816(o1, a[4], a[5], a[6], a[7], bf[0], bf[1]);
            mma16816(o2, a[8], a[9], a[10], a[11], bf[2], bf[3]);
            mma16816(o3, a[12], a[13], a[14], a[15], bf[2], bf[3]);
        }
        if (t < 2)
            st_pub4(o_dst, tagf((o0[0] + o2[0]) * inv_l, tag), tagf((o0[2] + o2[2]) * inv_l, tag),
                    tagf((o1[0] + o3[0]) * inv_l, tag), tagf((o1[2] + o3[2]) * inv_l, tag));
        if (threadIdx.x == 0) TS(6);
        if (warp < 7) {
#pragma unroll
            for (int ks = 0; ks < 8; ks++) {
                if ((ks & 1) == 0) mbar_wait(bars + 8 * (B_WO + (ks >> 1)));
                ldsm4t(wa + ks * 16 * WO_ROWB, bf[4 * ks], bf[4 * ks + 1], bf[4 * ks + 2], bf[4 * ks + 3]);
            }
            if (threadIdx.x == 0) TS(7);
            bar_sync(4, 384);
            float a[4] = {0.f, 0.f, 0.f, 0.f}, b[4] = {0.f, 0.f, 0.f, 0.f};
            float d[4] = {0.f, 0.f, 0.f, 0.f}, e[4] = {0.f, 0.f, 0.f, 0.f};
            uint32_t ob[16];
#pragma unroll
            for (int i = 0; i < 4; i++) ldsm4(oa + i * 64, ob[4 * i], ob[4 * i + 1], ob[4 * i + 2], ob[4 * i + 3]);
#pragma unroll
            for (int i = 0; i < 2; i++) {
                mma16816(a, bf[16 * i], bf[16 * i + 1], bf[16 * i + 2], bf[16 * i + 3], ob[8 * i], ob[8 * i + 1]);
                mma16816(b, bf[16 * i + 4], bf[16 * i + 5], bf[16 * i + 6], bf[16 * i + 7], ob[8 * i + 2], ob[8 * i + 3]);
                mma16816(d, bf[16 * i + 8], bf[16 * i + 9], bf[16 * i + 10], bf[16 * i + 11], ob[8 * i + 4], ob[8 * i + 5]);
                mma16816(e, bf[16 * i + 12], bf[16 * i + 13], bf[16 * i + 14], bf[16 * i + 15], ob[8 * i + 6], ob[8 * i + 7]);
            }
            const float r0 = (a[0] + b[0]) + (d[0] + e[0]), r1 = (a[2] + b[2]) + (d[2] + e[2]);
            if (threadIdx.x == 0) TS(9);
            float p0, p1, pn, pz;
            asm volatile("atom.relaxed.gpu.global.add.v4.f32 {%0,%1,%2,%3}, [%4], {%5,%6,%7,%8};"
                         : "=f"(p0), "=f"(p1), "=f"(pn), "=f"(pz) : "l"(acc_dst), "f"(r0), "f"(r1), "f"(1.0f), "f"(0.0f) : "memory");
            if (pn == 31.0f) {
                out_dst[0] = __float2bfloat16_rn(p0 + r0);
                out_dst[8] = __float2bfloat16_rn(p1 + r1);
            }
        }
        if (threadIdx.x == 0) { TS(10); TS_FLUSH(4); TS_FLUSH(6); TS_FLUSH(7); TS_FLUSH(9); TS_FLUSH(10); }
    } else if (warp == 13) {
        if (c < 112) st_pub(reinterpret_cast<uint32_t*>(&g_s.acc[c * ACC_STRIDE + lane]), 0u);
        asm volatile("fence.acq_rel.gpu;" ::: "memory");
        __syncwarp();
        if (lane == 0) red_inc(&g_s.cnt_z[0]);
        mbar_wait(bars + 8 * (B_K0 + 3));
        wait_count(&g_s.cnt_z[0], epoch * 128u);
        asm volatile("fence.acq_rel.gpu;" ::: "memory");
        if (lane == 0) { TS(12); TS_FLUSH(12); }
        bar_arrive(4, 384);
    } else {
        const int w = warp - 8, xt = threadIdx.x - 256;
        const uint32_t qtag = epoch << 16;

        bar_sync(1, 384);
        {
            const uint32_t ra = sb + OFF_RED + (w * 32 + lane) * 4;
            const float q = (lds32f(ra) + lds32f(ra + 512)) + (lds32f(ra + 1024) + lds32f(ra + 1536));
            st_pub(&g_s.q[w * 4096 + c * 32 + lane], qtag | bf16bits(q));
        }
        if (xt == 0) TS(2);
        {
            const uint32_t* src = &g_s.q[(j >> 2) * 4096 + hkv * 512 + xt * 4];
            mbar_wait(bars + 8 * prm.qgate);
            uint4 v;
            int it = 0;
            do {
                v = ld_poll4(src);
                if (++it > SPIN_LIMIT) __trap();
            } while (((((v.x ^ qtag) | (v.y ^ qtag)) | ((v.z ^ qtag) | (v.w ^ qtag))) >> 16) != 0u);
            sts64(sb + OFF_Q + (xt >> 6) * 528 + (xt & 63) * 8, __byte_perm(v.x, v.y, 0x5410), __byte_perm(v.z, v.w, 0x5410));
            bar_arrive(2, 384);
        }
        if (xt == 0) TS(3);
        float ws[4];
        {
            const uint32_t* src = &g_s.lse[(hkv * 16 + w * 4 + t) * 8 + (j >> 3)];
            mbar_wait(bars + 8 * prm.lgate);
            uint32_t v;
            int it = 0;
            do {
                v = ld_poll(src);
                if (++it > SPIN_LIMIT) __trap();
            } while ((v ^ tag) & 3u);
            __syncwarp();
            const float l = __uint_as_float(v);
            float m = fmaxf(l, __shfl_xor_sync(0xffffffffu, l, 1));
            m = fmaxf(m, __shfl_xor_sync(0xffffffffu, m, 2));
            float e = exp2f(l - m);
            float sum = e + __shfl_xor_sync(0xffffffffu, e, 1);
            sum += __shfl_xor_sync(0xffffffffu, sum, 2);
            e *= __frcp_rn(sum);
#pragma unroll
            for (int s = 0; s < 4; s++) ws[s] = __shfl_sync(0xffffffffu, e, s);
        }
        const uint32_t* o_src = &g_s.o[(hkv * 16 + w * 4) * 512 + (j >> 2) * 128 + lane * 4];
        uint32_t oa = sb + OFF_O + w * 272 + ((lane >> 3) * 32 + (lane & 7)) * 2;
        uint32_t target = epoch * 16u;
        pin(o_src); pin(cnt_src); pin(oa); pin(target);
        mbar_wait(bars + 8 * (B_V0 + 7));
        if (xt == 0) TS(5);
        wait_count(cnt_src, target);
        if (xt == 0) TS(11);
        uint4 v[4];
        gather4<512>(v, o_src, tag);
        float r0 = 0.f, r1 = 0.f, r2 = 0.f, r3 = 0.f;
#pragma unroll
        for (int s = 0; s < 4; s++) {
            r0 = fmaf(__uint_as_float(v[s].x), ws[s], r0);
            r1 = fmaf(__uint_as_float(v[s].y), ws[s], r1);
            r2 = fmaf(__uint_as_float(v[s].z), ws[s], r2);
            r3 = fmaf(__uint_as_float(v[s].w), ws[s], r3);
        }
        sts16(oa, bf16bits(r0));
        sts16(oa + 16, bf16bits(r1));
        sts16(oa + 32, bf16bits(r2));
        sts16(oa + 48, bf16bits(r3));
        bar_arrive(4, 384);
        if (xt == 0) { TS(8); TS_FLUSH(2); TS_FLUSH(3); TS_FLUSH(5); TS_FLUSH(8); TS_FLUSH(11); }
    }
}

typedef CUresult (*EncodeFn)(CUtensorMap*, CUtensorMapDataType, cuuint32_t, void*, const cuuint64_t*, const cuuint64_t*,
                             const cuuint32_t*, const cuuint32_t*, CUtensorMapInterleave, CUtensorMapSwizzle,
                             CUtensorMapL2promotion, CUtensorMapFloatOOBfill);

}

extern "C" void kernel_launch(void* const* d_in, const int* in_sizes, int n_in, void* d_out, int out_size) {
    (void)in_sizes; (void)n_in; (void)out_size;
    static EncodeFn enc = nullptr;
    if (!enc) {
        cudaDriverEntryPointQueryResult qr;
        cudaGetDriverEntryPoint("cuTensorMapEncodeTiled", (void**)&enc, cudaEnableDefault, &qr);
        cudaFuncSetAttribute(fused_decode_kernel, cudaFuncAttributeMaxDynamicSharedMemorySize, SMEM_BYTES);
    }
    Params prm;
    {
        static const uint16_t due[20] = {0, 0, 1900, 3210, 4520, 5830, 6485, 7140, 7795, 8450, 9105, 9760, 10415, 10970, 10970, 11625, 11625};
        static const int8_t dep[20] = {-1, -1, 0, 1, 2, 3, 3, 4, 4, 5, 6, 7, 8, 11, 11, 12, 12};
        for (int i = 0; i < 20; i++) { prm.due[i] = due[i]; prm.dep[i] = dep[i]; prm.order[i] = i; }
        prm.qgate = 2; prm.lgate = 9; prm.stagger = 0;
        prm.vptr = (const char*)d_in[2]; prm.woptr = (const char*)d_in[4];
    }
    const cuuint32_t es[3] = {1, 1, 1};
    {
        const cuuint64_t gd[3] = {4096, 224, 2};
        const cuuint64_t gs[2] = {8192, 224 * 8192};
        const cuuint32_t bd[3] = {32, 224, 2};
        enc(&prm.m[0], CU_TENSOR_MAP_DATA_TYPE_BFLOAT16, 3, d_in[3], gd, gs, bd, es, CU_TENSOR_MAP_INTERLEAVE_NONE,
            CU_TENSOR_MAP_SWIZZLE_64B, CU_TENSOR_MAP_L2_PROMOTION_L2_128B, CU_TENSOR_MAP_FLOAT_OOB_FILL_NONE);
    }
    {
        const cuuint64_t gd[3] = {64, 32 * 4096, 4};
        const cuuint64_t gs[2] = {512, 128};
        for (int i = 1; i <= 2; i++) {
            const cuuint32_t bd[3] = {64, i == 1 ? 64u : 32u, 4};
            enc(&prm.m[i], CU_TENSOR_MAP_DATA_TYPE_BFLOAT16, 3, d_in[i], gd, gs, bd, es, CU_TENSOR_MAP_INTERLEAVE_NONE,
                CU_TENSOR_MAP_SWIZZLE_128B, CU_TENSOR_MAP_L2_PROMOTION_L2_256B, CU_TENSOR_MAP_FLOAT_OOB_FILL_NONE);
        }
    }
    {
        const cuuint64_t gd[3] = {448, 4096, 1};
        const cuuint64_t gs[2] = {896, 896 * 4096};
        const cuuint32_t bd[3] = {120, 32, 1};
        enc(&prm.m[3], CU_TENSOR_MAP_DATA_TYPE_BFLOAT16, 3, d_in[4], gd, gs, bd, es, CU_TENSOR_MAP_INTERLEAVE_NONE,
            CU_TENSOR_MAP_SWIZZLE_NONE, CU_TENSOR_MAP_L2_PROMOTION_L2_128B, CU_TENSOR_MAP_FLOAT_OOB_FILL_NONE);
    }
    fused_decode_kernel<<<NCTA, NTHREADS, SMEM_BYTES, cudaStreamPerThread>>>(prm, (const __nv_bfloat16*)d_in[0], (__nv_bfloat16*)d_out);
}
```

```cpp
#include <cuda_runtime.h>
#include <cuda_bf16.h>
#include <cuda.h>
#include <stdint.h>

namespace {

constexpr int NCTA = 128;
constexpr int NTHREADS = 14 * 32;

constexpr uint32_t SB = 0x400;
constexpr int SLOT = 32768;
constexpr int OFF_WQ = 6 * SLOT;
constexpr int OFF_X = OFF_WQ + 28672;
constexpr int OFF_RED = OFF_X + 3584;
constexpr int OFF_Q = OFF_RED + 2048;
constexpr int OFF_STAT = OFF_Q + 1056;
constexpr int OFF_EPOCH = OFF_STAT + 128;
constexpr int OFF_BAR = OFF_EPOCH + 16;
constexpr int SMEM_BYTES = OFF_BAR + 176;
constexpr int OFF_P = OFF_WQ;
constexpr int OFF_O = OFF_P + 2048;
constexpr int OFF_WO = 2 * SLOT;
constexpr int WO_PIECE = 16384;
static_assert(SMEM_BYTES <= 232448, "smem");

enum { B_WQ = 0, B_K0 = 1, B_V0 = 5, B_WO = 13, NOPS = 15, NFULL = 17, B_FREE0 = 17, B_FREE1, B_FREE2, B_ORDY, B_GO };
constexpr uint32_t BARS = SB + OFF_BAR;

struct Scratch {
    float acc[16384];
    uint32_t cnt_o[2 * 1024];
    uint32_t o[128 * 512];
    uint32_t q[4 * 4096];
    uint64_t ml[NCTA * 4];
};
__device__ uint4 g_buf[(sizeof(Scratch) + 65536) / 16];
__device__ __forceinline__ int acc_line(int n) { return (n >> 4) * 2048 + (n & 16) * 64 + (n & 15) * 64; }

struct alignas(32) Op {
    uint32_t dst, bar;
    uint32_t map, row;
    uint32_t due;
    uint32_t depbar, late;
    uint32_t frebar;
};
struct Params {
    CUtensorMap m[4];
    Op op[NOPS];
};

constexpr int SPIN_LIMIT = 1 << 23;
constexpr int WAIT_LIMIT = 1 << 18;
constexpr float SCORE_SCALE = 0.0625f * 1.4426950408889634f;

__device__ __forceinline__ uint32_t gtime_lo() {
    uint32_t t;
    asm volatile("mov.u32 %0, %globaltimer_lo;" : "=r"(t));
    return t;
}
__device__ __forceinline__ void wait_until(uint32_t t0, uint32_t ns) {
    for (int it = 0; gtime_lo() - t0 < ns && it < SPIN_LIMIT; it++) {}
}
__device__ __forceinline__ void mbar_init(uint32_t bar, uint32_t cnt) {
    asm volatile("mbarrier.init.shared::cta.b64 [%0], %1;" ::"r"(bar), "r"(cnt) : "memory");
}
__device__ __forceinline__ void mbar_expect_tx(uint32_t bar, uint32_t bytes) {
    asm volatile("mbarrier.arrive.expect_tx.shared::cta.b64 _, [%0], %1;" ::"r"(bar), "r"(bytes) : "memory");
}
__device__ __forceinline__ void mbar_arrive(uint32_t bar) {
    asm volatile("mbarrier.arrive.shared::cta.b64 _, [%0];" ::"r"(bar) : "memory");
}
__device__ __forceinline__ void mbar_wait(uint32_t bar, uint32_t parity = 0) {
    uint32_t ok;
    int it = 0;
    do {
        asm volatile("{.reg .pred p; mbarrier.try_wait.parity.shared::cta.b64 p, [%1], %2; selp.u32 %0,1,0,p;}"
                     : "=r"(ok) : "r"(bar), "r"(parity) : "memory");
        if (++it > WAIT_LIMIT) __trap();
    } while (!ok);
}
__device__ __forceinline__ uint32_t mbar_test(uint32_t bar, uint32_t parity) {
    uint32_t ok;
    asm volatile("{.reg .pred p; mbarrier.test_wait.parity.shared::cta.b64 p, [%1], %2; selp.u32 %0,1,0,p;}"
                 : "=r"(ok) : "r"(bar), "r"(parity) : "memory");
    return ok;
}
__device__ __forceinline__ void tma3d(uint32_t dst, const CUtensorMap* tm, int c0, int c1, int c2, uint32_t bar) {
    asm volatile("cp.async.bulk.tensor.3d.shared::cluster.global.mbarrier::complete_tx::bytes [%0], [%1, {%3,%4,%5}], [%2];"
                 ::"r"(dst), "l"(tm), "r"(bar), "r"(c0), "r"(c1), "r"(c2) : "memory");
}
__device__ __forceinline__ void tma3d_elect(uint32_t dst, const CUtensorMap* tm, int c1, int c2, uint32_t bar, uint64_t pol) {
    asm volatile("{.reg .pred p;\n\t"
                 "elect.sync _|p, 0xffffffff;\n\t"
                 "@p cp.async.bulk.tensor.3d.shared::cluster.global.mbarrier::complete_tx::bytes.L2::cache_hint"
                 " [%0], [%1, {0,%3,%4}], [%2], %5;}"
                 ::"r"(dst), "l"(tm), "r"(bar), "r"(c1), "r"(c2), "l"(pol) : "memory");
}
__device__ __forceinline__ void bulk_g2s(uint32_t dst, const void* src, uint32_t bytes, uint32_t bar) {
    asm volatile("cp.async.bulk.shared::cluster.global.mbarrier::complete_tx::bytes [%0], [%1], %2, [%3];"
                 ::"r"(dst), "l"(src), "r"(bytes), "r"(bar) : "memory");
}
__device__ __forceinline__ void ldsm4(uint32_t addr, uint32_t* r) {
    asm volatile("ldmatrix.sync.aligned.m8n8.x4.shared.b16 {%0,%1,%2,%3}, [%4];"
                 : "=r"(r[0]), "=r"(r[1]), "=r"(r[2]), "=r"(r[3]) : "r"(addr) : "memory");
}
__device__ __forceinline__ void ldsm2(uint32_t addr, uint32_t* r) {
    asm volatile("ldmatrix.sync.aligned.m8n8.x2.shared.b16 {%0,%1}, [%2];" : "=r"(r[0]), "=r"(r[1]) : "r"(addr) : "memory");
}
__device__ __forceinline__ void ldsm4t(uint32_t addr, uint32_t* r) {
    asm volatile("ldmatrix.sync.aligned.m8n8.x4.trans.shared.b16 {%0,%1,%2,%3}, [%4];"
                 : "=r"(r[0]), "=r"(r[1]), "=r"(r[2]), "=r"(r[3]) : "r"(addr) : "memory");
}
__device__ __forceinline__ void mma16816(float (&c)[4], const uint32_t* a, const uint32_t* b) {
    asm volatile("mma.sync.aligned.m16n8k16.row.col.f32.bf16.bf16.f32 {%0,%1,%2,%3}, {%4,%5,%6,%7}, {%8,%9}, {%0,%1,%2,%3};"
                 : "+f"(c[0]), "+f"(c[1]), "+f"(c[2]), "+f"(c[3])
                 : "r"(a[0]), "r"(a[1]), "r"(a[2]), "r"(a[3]), "r"(b[0]), "r"(b[1]));
}
__device__ __forceinline__ void bar_sync(int id, int n) { asm volatile("bar.sync %0, %1;" ::"r"(id), "r"(n) : "memory"); }
__device__ __forceinline__ void bar_arrive(int id, int n) { asm volatile("bar.arrive %0, %1;" ::"r"(id), "r"(n) : "memory"); }
__device__ __forceinline__ uint32_t ld_poll(const uint32_t* p) {
    uint32_t v;
    asm volatile("ld.relaxed.gpu.global.u32 %0, [%1];" : "=r"(v) : "l"(p) : "memory");
    return v;
}
__device__ __forceinline__ uint4 ld_poll4(const uint32_t* p) {
    uint4 v;
    asm volatile("ld.relaxed.gpu.global.v4.u32 {%0,%1,%2,%3}, [%4];"
                 : "=r"(v.x), "=r"(v.y), "=r"(v.z), "=r"(v.w) : "l"(p) : "memory");
    return v;
}
__device__ __forceinline__ void st_pub(uint32_t* p, uint32_t v) {
    asm volatile("st.relaxed.gpu.global.u32 [%0], %1;" ::"l"(p), "r"(v) : "memory");
}
__device__ __forceinline__ void sts16(uint32_t addr, uint16_t v) { asm volatile("st.shared.u16 [%0], %1;" ::"r"(addr), "h"(v) : "memory"); }
__device__ __forceinline__ void sts32(uint32_t addr, uint32_t v) { asm volatile("st.shared.u32 [%0], %1;" ::"r"(addr), "r"(v) : "memory"); }
__device__ __forceinline__ void sts32f(uint32_t addr, float v) { asm volatile("st.shared.f32 [%0], %1;" ::"r"(addr), "f"(v) : "memory"); }
__device__ __forceinline__ void sts64(uint32_t addr, uint32_t a, uint32_t b) {
    asm volatile("st.shared.v2.u32 [%0], {%1,%2};" ::"r"(addr), "r"(a), "r"(b) : "memory");
}
__device__ __forceinline__ uint32_t lds32(uint32_t addr) {
    uint32_t v;
    asm volatile("ld.shared.u32 %0, [%1];" : "=r"(v) : "r"(addr) : "memory");
    return v;
}
__device__ __forceinline__ float lds32f(uint32_t addr) { return __uint_as_float(lds32(addr)); }
__device__ __forceinline__ uint16_t bf16bits(float v) { return __bfloat16_as_ushort(__float2bfloat16_rn(v)); }
__device__ __forceinline__ uint32_t pack_bf16(float lo, float hi) {
    uint32_t r;
    asm("cvt.rn.bf16x2.f32 %0, %1, %2;" : "=r"(r) : "f"(hi), "f"(lo));
    return r;
}
__device__ __forceinline__ uint32_t tagf(float v, uint32_t epoch) { return (__float_as_uint(v) & ~3u) | (epoch & 3u); }
__device__ __forceinline__ float acc_tag(uint32_t epoch) { return (float)(epoch & 0xffffu); }

__device__ __forceinline__ uint32_t acc_add(float* acc, __nv_bfloat16* out, float r0, float r1, float etag) {
    uint32_t stale;
    asm volatile("{\n\t.reg .f32 p0, p1, pn, pz;\n\t.reg .pred ok, last;\n\t.reg .b16 h0, h1;\n\t"
                 "atom.relaxed.gpu.global.add.v4.f32 {p0,p1,pn,pz}, [%1], {%3,%4,0f3F800000,0f00000000};\n\t"
                 "setp.eq.f32 ok, pz, %5;\n\t"
                 "setp.eq.and.f32 last, pn, 0f41F80000, ok;\n\t"
                 "add.f32 p0, p0, %3;\n\tadd.f32 p1, p1, %4;\n\t"
                 "cvt.rn.bf16.f32 h0, p0;\n\tcvt.rn.bf16.f32 h1, p1;\n\t"
                 "@last st.global.b16 [%2], h0;\n\t@last st.global.b16 [%2+16], h1;\n\t"
                 "selp.u32 %0, 0, 1, ok;\n\t}"
                 : "=r"(stale) : "l"(acc), "l"(out), "f"(r0), "f"(r1), "f"(etag) : "memory");
    return stale;
}

__device__ __noinline__ void acc_retry(float* acc, __nv_bfloat16* out, float r0, float r1, float etag) {
#pragma unroll 1
    for (int it = 0; it < SPIN_LIMIT; it++)
        if (!acc_add(acc, out, r0, r1, etag)) return;
    __trap();
}

template <int PIECE>
__device__ __forceinline__ void o_phase(uint32_t wa, uint32_t oa, float* acc, __nv_bfloat16* out, float etag) {
    uint32_t wf[32], of[16];
    constexpr int NCH = PIECE == 0 ? 4 : 2;
    float d[NCH][4];
#pragma unroll
    for (int i = 0; i < NCH; i++) d[i][0] = d[i][1] = d[i][2] = d[i][3] = 0.f;
#pragma unroll
    for (int step = 0; step < 2; step++) {
        if (step == PIECE) {
#pragma unroll
            for (int ks = 0; ks < 8; ks++) {
                if ((ks & 3) == 0) mbar_wait(BARS + 8 * (B_WO + PIECE * 2 + (ks >> 2)));
                ldsm4t(wa + ks * 2048, &wf[4 * ks]);
            }
        } else {
            mbar_wait(BARS + 8 * B_ORDY);
#pragma unroll
            for (int i = 0; i < 4; i++) ldsm4(oa + i * 64, &of[4 * i]);
        }
    }
#pragma unroll
    for (int ks = 0; ks < 8; ks++) mma16816(d[ks % NCH], wf + 4 * ks, of + 2 * ks);
    float r0, r1;
    if (NCH == 4) {
        r0 = (d[0][0] + d[1][0]) + (d[2 % NCH][0] + d[3 % NCH][0]);
        r1 = (d[0][2] + d[1][2]) + (d[2 % NCH][2] + d[3 % NCH][2]);
    } else {
        r0 = d[0][0] + d[1][0];
        r1 = d[0][2] + d[1][2];
    }
    if (__builtin_expect(acc_add(acc, out, r0, r1, etag), 0)) acc_retry(acc, out, r0, r1, etag);
}

__device__ __forceinline__ void poll_go(const uint32_t* cnt, uint32_t target) {
#pragma unroll 1
    for (int it = 0; it < SPIN_LIMIT; it++) {
        uint32_t v;
        asm volatile("{.reg .pred p;\n\t"
                     "ld.relaxed.gpu.global.u32 %0, [%1];\n\t"
                     "setp.eq.u32 p, %0, %2;\n\t"
                     "@p mbarrier.complete_tx.relaxed.cta.shared::cta.b64 [%3], 1;}"
                     : "=&r"(v) : "l"(cnt), "r"(target), "r"(BARS + 8 * B_GO) : "memory");
        if (v == target) return;
    }
    __trap();
}

template <typename T> __device__ __forceinline__ void pin(T*& p) { asm volatile("" : "+l"(p)); }
__device__ __forceinline__ void pin(uint32_t& v) { asm volatile("" : "+r"(v)); }

__device__ __forceinline__ int kv_row0(int c) { return (((c >> 2) & 3) * 8 + (c >> 4)) * 4096 + 3072 + (c & 3) * 256; }

__global__ void __launch_bounds__(NTHREADS, 1)
fused_decode_kernel(const char* __restrict__ wq, const __nv_bfloat16* __restrict__ x, __nv_bfloat16* __restrict__ out,
                    Scratch* __restrict__ scr, const __grid_constant__ Params prm) {
    extern __shared__ __align__(1024) uint8_t smem_raw[];
    asm volatile("prefetch.global.L2 [%0];" ::"l"(wq + (size_t)(blockIdx.x * NTHREADS + threadIdx.x) * 64) : "memory");
    const int c = blockIdx.x;
    if (threadIdx.x == 0) {
        mbar_init(BARS + 8 * B_WQ, 1);
        mbar_init(BARS + 8 * B_K0, 1);
        asm volatile("fence.proxy.async.shared::cta;" ::: "memory");
        mbar_expect_tx(BARS + 8 * B_WQ, 28672 + 3584);
        tma3d(SB + OFF_WQ, &prm.m[0], c * 32, 0, 0, BARS + 8 * B_WQ);
        bulk_g2s(SB + OFF_X, x, 3584, BARS + 8 * B_WQ);
        mbar_expect_tx(BARS + 8 * B_K0, SLOT);
        tma3d(SB, &prm.m[1], 0, kv_row0(c), 0, BARS + 8 * B_K0);
#pragma unroll
        for (int i = 2; i < NFULL; i++) mbar_init(BARS + 8 * i, 1);
        mbar_init(BARS + 8 * B_FREE0, 4);
        mbar_init(BARS + 8 * B_FREE1, 4);
        mbar_init(BARS + 8 * B_FREE2, 4);
        mbar_init(BARS + 8 * B_ORDY, 128);
        mbar_init(BARS + 8 * B_GO, 1);
        mbar_expect_tx(BARS + 8 * B_GO, 1);
        asm volatile("fence.proxy.async.shared::cta;" ::: "memory");
    }
    const uint32_t t_start = gtime_lo();
    const int hkv = c >> 4, j = c & 15;
    const int warp = __shfl_sync(0xffffffffu, threadIdx.x >> 5, 0), lane = threadIdx.x & 31;
    const int g = lane >> 2, t = lane & 3;
    __syncthreads();

    if (warp == 12) {
        if ((uint32_t)__cvta_generic_to_shared(smem_raw) != SB) __trap();
        if (lane >= 2 && lane < NFULL) mbar_expect_tx(BARS + 8 * lane, lane < B_V0 ? SLOT : (lane < B_WO ? SLOT / 2 : SLOT / 4));
        __syncwarp();
        const int row0 = kv_row0(c);
        uint64_t pol;
        asm volatile("createpolicy.fractional.L2::evict_first.b64 %0, 1.0;" : "=l"(pol));
#pragma unroll 1
        for (int i = 2; i < NOPS; i++) {
            const Op op = prm.op[i];
            const CUtensorMap* tm = (const CUtensorMap*)((const char*)prm.m + op.map);
            const int c1 = (i >= B_WO ? (c >> 2) * 128 : row0) + op.row;
            const int c2 = i >= B_WO ? (c & 3) * 2 + ((i - B_WO) ^ ((c >> 2) & 1)) : 0;
            asm volatile("prefetch.tensormap [%0];" ::"l"(tm) : "memory");
            mbar_wait(op.frebar, op.frebar == op.bar);
            wait_until(t_start, op.due);
            bool expired;
            uint32_t ok;
            int it = 0;
            do {
                expired = gtime_lo() - t_start >= op.late || ++it > SPIN_LIMIT;
                ok = mbar_test(op.depbar, 0);
            } while (!ok && !expired);
            tma3d_elect(op.dst, tm, c1, c2, op.bar, pol);
            if (i >= B_WO) tma3d_elect(op.dst + WO_PIECE / 2, tm, c1 + 64, c2, op.bar + 8, pol);
        }
        if (lane == 0) poll_go(&scr->cnt_o[1024 + hkv * 32], lds32(SB + OFF_EPOCH) * 16u);
    } else if (warp < 8) {
        uint32_t bf[32];
        {
            float acc[4] = {0.f, 0.f, 0.f, 0.f};
            const int d0 = (warp >> 1) * 112;
            const int ar = d0 + (lane & 7) + ((lane >> 4) << 3);
            const int ach = (warp & 1) * 2 + ((lane >> 3) & 1);
            const uint32_t aaddr = SB + OFF_WQ + ar * 64 + ((ach ^ ((ar >> 1) & 3)) << 4);
            const uint32_t baddr = SB + OFF_X + ((lane & 7) >> 1) * 896 + d0 * 2 + ((lane >> 3) & 1) * 16;
            mbar_wait(BARS + 8 * B_WQ);
#pragma unroll
            for (int ks = 0; ks < 7; ks++) {
                uint32_t a[4], b[2];
                ldsm4t(aaddr + ks * 1024, a);
                ldsm2(baddr + ks * 32, b);
                mma16816(acc, a, b);
            }
            const uint32_t raddr = SB + OFF_RED + (((warp >> 1) * 4 + t) * 32 + (warp & 1) * 16 + g) * 4;
            sts32f(raddr, acc[0]);
            sts32f(raddr + 32, acc[2]);
            bar_arrive(1, 384);
        }
        bar_sync(2, 384);
        const uint32_t epoch = lds32(SB + OFF_EPOCH);
        {
            const uint32_t qaddr = SB + OFF_Q + ((lane >> 1) & 1) * 528 + (lane >> 3) * 16;
#pragma unroll
            for (int i = 0; i < 8; i++) ldsm4(qaddr + i * 64, &bf[4 * i]);
        }
        float sc[4] = {0.f, 0.f, 0.f, 0.f};
        {
            const int kr = (warp & 3) * 16 + (lane & 7) + ((lane >> 3) & 1) * 8;
            const int chi = lane >> 4, sw = lane & 7;
#pragma unroll 1
            for (int r = 0; r < 2; r++) {
                const int chunk = (warp >> 2) + 2 * r;
                const uint32_t kbase = SB + chunk * SLOT + kr * 128;
                mbar_wait(BARS + 8 * (B_K0 + chunk));
                float s0[4] = {0.f, 0.f, 0.f, 0.f}, s1[4] = {0.f, 0.f, 0.f, 0.f};
#pragma unroll
                for (int ks = 0; ks < 16; ks += 2) {
                    uint32_t a[4], e[4];
                    ldsm4(kbase + (ks >> 2) * 8192 + ((((ks & 3) * 2 + chi) ^ sw) << 4), a);
                    ldsm4(kbase + (ks >> 2) * 8192 + ((((ks & 3) * 2 + 2 + chi) ^ sw) << 4), e);
                    mma16816(s0, a, &bf[2 * ks]);
                    mma16816(s1, e, &bf[2 * ks + 2]);
                }
                sc[0] = sc[2];
                sc[1] = sc[3];
                sc[2] = __bfloat162float(__float2bfloat16_rn(s0[0] + s1[0]));
                sc[3] = __bfloat162float(__float2bfloat16_rn(s0[2] + s1[2]));
                __syncwarp();
                if (lane == 0 && chunk < 3) mbar_arrive(BARS + 8 * (B_FREE0 + chunk));
            }
        }
        {
            float m = fmaxf(fmaxf(sc[0], sc[1]), fmaxf(sc[2], sc[3]));
            m = fmaxf(m, __shfl_xor_sync(0xffffffffu, m, 4));
            m = fmaxf(m, __shfl_xor_sync(0xffffffffu, m, 8));
            m = fmaxf(m, __shfl_xor_sync(0xffffffffu, m, 16));
            if (lane < 2) sts32f(SB + OFF_STAT + (warp * 2 + lane) * 4, m);
            bar_sync(3, 256);
#pragma unroll
            for (int w = 0; w < 8; w++) m = fmaxf(m, lds32f(SB + OFF_STAT + (w * 2 + (t & 1)) * 4));
            float l = 0.f;
            const uint32_t paddr = SB + OFF_P + (t & 1) * 528 + ((warp >> 2) * 64 + (warp & 3) * 16 + g) * 2;
#pragma unroll
            for (int i = 0; i < 4; i++) {
                const float p = exp2f((sc[i] - m) * SCORE_SCALE);
                l += p;
                if (t < 2) sts16(paddr + (i >> 1) * 256 + (i & 1) * 16, bf16bits(p));
            }
            l += __shfl_xor_sync(0xffffffffu, l, 4);
            l += __shfl_xor_sync(0xffffffffu, l, 8);
            l += __shfl_xor_sync(0xffffffffu, l, 16);
            if (lane < 2) sts32f(SB + OFF_STAT + 64 + (warp * 2 + lane) * 4, l);
            bar_sync(3, 256);
            if (threadIdx.x < 4) {
                l = 0.f;
#pragma unroll
                for (int w = 0; w < 8; w++) l += lds32f(SB + OFF_STAT + 64 + (w * 2 + (t & 1)) * 4);
                const uint64_t v = ((uint64_t)__float_as_uint(m) << 32) | tagf(l, epoch);
                asm volatile("st.relaxed.gpu.global.b64 [%0], %1;" ::"l"(&scr->ml[c * 4 + lane]), "l"(v) : "memory");
            }
        }
        uint32_t v0, v1, pa, wa, oa;
        {
            const int vr = (lane & 7) + ((lane >> 4) << 3);
            const int ch = (warp & 1) * 4 + ((lane >> 3) & 1);
            v0 = SB + (warp >> 1) * 4096 + vr * 128 + ((ch ^ (lane & 7)) << 4);
            v1 = SB + (warp >> 1) * 4096 + vr * 128 + (((ch + 2) ^ (lane & 7)) << 4);
            pa = SB + OFF_P + ((lane >> 1) & 1) * 528 + (lane >> 3) * 16;
            wa = SB + OFF_WO + (warp >> 2) * WO_PIECE + vr * 128 + ((((warp & 3) * 2 + ((lane >> 3) & 1)) ^ (lane & 7)) << 4);
            oa = SB + OFF_O + ((lane & 7) >> 1) * 272 + (lane >> 3) * 16;
        }
        const int mt = (j & 3) * 8 + (warp ^ (j & 4));
        uint32_t* o_dst = &scr->o[((hkv * 4 + (t & 1) * 2 + (warp >> 2)) * 16 + j) * 128 + (warp & 3) * 32 + (t >> 1) * 16 + g];
        float* acc_dst = &scr->acc[acc_line(mt * 4 + (lane >> 3)) + (lane & 7) * 4];
        __nv_bfloat16* out_dst = out + (t * 28 + mt) * 16 + g;
        const float etag = acc_tag(epoch);
        pin(v0); pin(v1); pin(pa); pin(wa); pin(oa); pin(o_dst); pin(acc_dst); pin(out_dst);
        float o0[4] = {0.f, 0.f, 0.f, 0.f}, o1[4] = {0.f, 0.f, 0.f, 0.f};
        float o2[4] = {0.f, 0.f, 0.f, 0.f}, o3[4] = {0.f, 0.f, 0.f, 0.f};
#pragma unroll 1
        for (int cq = 0; cq < 8; cq++) {
            const uint32_t so = ((cq < 4) ? 8 + cq : cq - 4) * (SLOT / 2);
            ldsm4(pa + cq * 64, bf);
            uint32_t va = v0 + so, vb = v1 + so;
            pin(va); pin(vb);
            mbar_wait(BARS + 8 * (B_V0 + cq));
            uint32_t a[16];
            ldsm4t(va, a);
            ldsm4t(vb, a + 4);
            ldsm4t(va + 2048, a + 8);
            ldsm4t(vb + 2048, a + 12);
            mma16816(o0, a, bf);
            mma16816(o1, a + 4, bf);
            mma16816(o2, a + 8, bf + 2);
            mma16816(o3, a + 12, bf + 2);
        }
        st_pub(o_dst, tagf(t < 2 ? o0[0] + o2[0] : o1[0] + o3[0], epoch));
        st_pub(o_dst + 8, tagf(t < 2 ? o0[2] + o2[2] : o1[2] + o3[2], epoch));
        if (mt >= 28) {
            mbar_wait(BARS + 8 * (B_WO + (warp >> 2) * 2));
            mbar_wait(BARS + 8 * (B_WO + (warp >> 2) * 2 + 1));
        } else if (warp < 4) {
            o_phase<0>(wa, oa, acc_dst, out_dst, etag);
        } else {
            o_phase<1>(wa, oa, acc_dst, out_dst, etag);
        }
    } else {
        const uint32_t* cnt = &scr->cnt_o[(lane & 1) * 1024 + hkv * 32];
        const uint32_t epoch = (ld_poll(cnt) >> 4) + 1u;
        if (warp == 13) {
            if (c < 112 && lane < 8)
                asm volatile("st.relaxed.gpu.global.v4.f32 [%0], {%1,%1,%1,%2};"
                             ::"l"(&scr->acc[acc_line(c) + lane * 4]), "f"(0.f), "f"(acc_tag(epoch)) : "memory");
            pin(cnt);
            if (lane < 2) {
                mbar_wait(BARS + 8 * (B_V0 + 7));
                asm volatile("red.relaxed.gpu.global.add.u32 [%0], 1;" ::"l"(cnt) : "memory");
                if (lane == 0) poll_go(cnt, lds32(SB + OFF_EPOCH) * 16u);
            }
            return;
        }
        const int w = warp - 8, xt = threadIdx.x - 256;
        const uint32_t qtag = epoch << 16;
        if (xt == 0) sts32(SB + OFF_EPOCH, epoch);
        bar_sync(1, 384);
        {
            const uint32_t ra = SB + OFF_RED + (w * 32 + lane) * 4;
            const float q = (lds32f(ra) + lds32f(ra + 512)) + (lds32f(ra + 1024) + lds32f(ra + 1536));
            st_pub(&scr->q[w * 4096 + c * 32 + lane], qtag | bf16bits(q));
        }
        {
            const uint32_t* src = &scr->q[(j >> 2) * 4096 + hkv * 512 + xt * 4];
            mbar_wait(BARS + 8 * (B_K0 + 1));
            wait_until(t_start, 5000);
            uint4 v;
            int it = 0;
            do {
                v = ld_poll4(src);
                if (++it > SPIN_LIMIT) __trap();
            } while (((((v.x ^ qtag) | (v.y ^ qtag)) | ((v.z ^ qtag) | (v.w ^ qtag))) >> 16) != 0u);
            sts64(SB + OFF_Q + (xt >> 6) * 528 + (xt & 63) * 8, __byte_perm(v.x, v.y, 0x5410), __byte_perm(v.z, v.w, 0x5410));
            bar_arrive(2, 384);
        }
        float ws[4];
        {
            const uint64_t* src = &scr->ml[(hkv * 16 + w * 4 + t) * 4 + (j >> 3)];
            mbar_wait(BARS + 8 * (B_V0 + 4));
            uint64_t v;
            int it = 0;
            do {
                asm volatile("ld.relaxed.gpu.global.b64 %0, [%1];" : "=l"(v) : "l"(src) : "memory");
                if (++it > SPIN_LIMIT) __trap();
            } while (((uint32_t)v ^ epoch) & 3u);
            __syncwarp();
            const float ms = __uint_as_float((uint32_t)(v >> 32));
            float m = fmaxf(ms, __shfl_xor_sync(0xffffffffu, ms, 1));
            m = fmaxf(m, __shfl_xor_sync(0xffffffffu, m, 2));
            float e = exp2f((ms - m) * SCORE_SCALE);
            float sum = e * __uint_as_float((uint32_t)v);
            sum += __shfl_xor_sync(0xffffffffu, sum, 1);
            sum += __shfl_xor_sync(0xffffffffu, sum, 2);
            e *= __frcp_rn(sum);
#pragma unroll
            for (int s = 0; s < 4; s++) ws[s] = __shfl_sync(0xffffffffu, e, s);
        }
        const uint32_t* o_src = &scr->o[((c >> 2) * 16 + w * 4) * 128 + lane * 4];
        uint32_t oa = SB + OFF_O + w * 272 + lane * 8;
        pin(o_src); pin(oa);
        mbar_wait(BARS + 8 * B_GO);
#pragma unroll 1
        for (int it = 0; it < SPIN_LIMIT; it++) {
            uint4 v[4];
#pragma unroll
            for (int s = 0; s < 4; s++) v[s] = ld_poll4(o_src + s * 128);
            float r0 = 0.f, r1 = 0.f, r2 = 0.f, r3 = 0.f;
            uint32_t d[4];
#pragma unroll
            for (int s = 0; s < 4; s++) {
                r0 = fmaf(__uint_as_float(v[s].x), ws[s], r0);
                r1 = fmaf(__uint_as_float(v[s].y), ws[s], r1);
                r2 = fmaf(__uint_as_float(v[s].z), ws[s], r2);
                r3 = fmaf(__uint_as_float(v[s].w), ws[s], r3);
                d[s] = ((v[s].x ^ epoch) | (v[s].y ^ epoch)) | ((v[s].z ^ epoch) | (v[s].w ^ epoch));
            }
            sts64(oa, pack_bf16(r0, r1), pack_bf16(r2, r3));
            const uint32_t bad = ((d[0] | d[1]) | (d[2] | d[3])) & 3u;
            asm volatile("{.reg .pred p; setp.eq.u32 p, %1, 0; @p mbarrier.arrive.shared::cta.b64 _, [%0];}"
                         ::"r"(BARS + 8 * B_ORDY), "r"(bad) : "memory");
            if (!bad) return;
        }
        __trap();
    }
}

typedef CUresult (*EncodeFn)(CUtensorMap*, CUtensorMapDataType, cuuint32_t, void*, const cuuint64_t*, const cuuint64_t*,
                             const cuuint32_t*, const cuuint32_t*, CUtensorMapInterleave, CUtensorMapSwizzle,
                             CUtensorMapL2promotion, CUtensorMapFloatOOBfill);

}

extern "C" void kernel_launch(void* const* d_in, const int* in_sizes, int n_in, void* d_out, int out_size) {
    (void)in_sizes; (void)n_in; (void)out_size;
    static EncodeFn enc = nullptr;
    static Scratch* scr = nullptr;
    if (!enc) {
        void* base = nullptr;
        cudaGetSymbolAddress(&base, g_buf);
        scr = (Scratch*)(((uintptr_t)base + 65535) & ~(uintptr_t)65535);
        cudaDriverEntryPointQueryResult qr;
        cudaGetDriverEntryPoint("cuTensorMapEncodeTiled", (void**)&enc, cudaEnableDefault, &qr);
        cudaFuncSetAttribute(fused_decode_kernel, cudaFuncAttributeMaxDynamicSharedMemorySize, SMEM_BYTES);
    }
    Params prm;
    {
        const int dep[NOPS] = {0, 0, 0, 1, 2, 3, 3, 4, 4, 5, 6, 7, 8, 11, 12};
        for (int i = 0; i < NOPS; i++) {
            Op& op = prm.op[i];
            const bool isk = i < B_V0, iso = i >= B_WO;
            op.dst = SB + (isk ? (i - B_K0) * SLOT : (iso ? OFF_WO + (i - B_WO) * WO_PIECE : ((i - B_V0 + 8) % 12) * (SLOT / 2)));
            op.map = (isk ? 1 : (iso ? 3 : 2)) * sizeof(CUtensorMap);
            op.row = isk ? (i - B_K0) * 64 : (iso ? 0 : (i - B_V0) * 32);
            op.due = (i < 2 || iso) ? 0 : (isk ? 1740 + (i - 2) * 1310 : 5670 + (i - B_V0) * 658);
            op.depbar = BARS + 8 * dep[i];
            op.late = iso ? 11650 + (i - B_WO) * 600 : 100000;
            op.frebar = BARS + 8 * (i >= B_V0 + 4 ? B_FREE0 + ((i - B_V0 - 4) >> 1) : i);
            op.bar = BARS + 8 * (iso ? B_WO + 2 * (i - B_WO) : i);
        }
    }
    const cuuint32_t es[3] = {1, 1, 1};
    {
        const cuuint64_t gd[3] = {4096, 224, 2};
        const cuuint64_t gs[2] = {8192, 224 * 8192};
        const cuuint32_t bd[3] = {32, 224, 2};
        enc(&prm.m[0], CU_TENSOR_MAP_DATA_TYPE_BFLOAT16, 3, d_in[3], gd, gs, bd, es, CU_TENSOR_MAP_INTERLEAVE_NONE,
            CU_TENSOR_MAP_SWIZZLE_64B, CU_TENSOR_MAP_L2_PROMOTION_L2_128B, CU_TENSOR_MAP_FLOAT_OOB_FILL_NONE);
    }
    for (int i = 1; i <= 2; i++) {
        const cuuint64_t gd[3] = {64, 32 * 4096, 4};
        const cuuint64_t gs[2] = {512, 128};
        const cuuint32_t bd[3] = {64, i == 1 ? 64u : 32u, 4};
        enc(&prm.m[i], CU_TENSOR_MAP_DATA_TYPE_BFLOAT16, 3, d_in[i], gd, gs, bd, es, CU_TENSOR_MAP_INTERLEAVE_NONE,
            CU_TENSOR_MAP_SWIZZLE_128B, CU_TENSOR_MAP_L2_PROMOTION_L2_256B, CU_TENSOR_MAP_FLOAT_OOB_FILL_NONE);
    }
    {
        const cuuint64_t gd[3] = {64, 4096, 7};
        const cuuint64_t gs[2] = {896, 128};
        const cuuint32_t bd[3] = {64, 64, 1};
        enc(&prm.m[3], CU_TENSOR_MAP_DATA_TYPE_BFLOAT16, 3, d_in[4], gd, gs, bd, es, CU_TENSOR_MAP_INTERLEAVE_NONE,
            CU_TENSOR_MAP_SWIZZLE_128B, CU_TENSOR_MAP_L2_PROMOTION_NONE, CU_TENSOR_MAP_FLOAT_OOB_FILL_NONE);
    }
    cudaLaunchConfig_t cfg = {};
    cfg.gridDim = dim3(NCTA);
    cfg.blockDim = dim3(NTHREADS);
    cfg.dynamicSmemBytes = SMEM_BYTES;
    cfg.stream = cudaStreamPerThread;
    cudaLaunchAttribute attr;
    attr.id = cudaLaunchAttributeCooperative;
    attr.val.cooperative = 1;
    cfg.attrs = &attr;
    cfg.numAttrs = 1;
    cudaLaunchKernelEx(&cfg, fused_decode_kernel, (const char*)d_in[3], (const __nv_bfloat16*)d_in[0], (__nv_bfloat16*)d_out, scr, prm);
}
```
